```python
import torch

def _softmax(x, axis=-1):
    return torch.softmax(x, dim=axis)
def _gelu(x):
    return torch.nn.functional.gelu(x, approximate="tanh")
def _silu(x):
    return torch.nn.functional.silu(x)
def _sigmoid(x):
    return torch.sigmoid(x)
def _layernorm(x, axis=-1, eps=1e-5):
    m = x.mean(dim=axis, keepdim=True)
    v = x.var(dim=axis, keepdim=True, unbiased=False)
    return (x - m) / torch.sqrt(v + eps)
def _scatter_add(tgt, idx, src, axis=0):
    return tgt.clone().index_add_(axis, idx, src)
def _segment_sum(src, seg, n):
    out = torch.zeros((n,) + src.shape[1:], dtype=src.dtype)
    return out.index_add_(0, seg, src)
def _pad(x, pw):
    flat = tuple(v for pair in reversed(pw) for v in pair)
    return torch.nn.functional.pad(x, flat)

kernel_name = 'standalone__layernorm_linear__prompt'

def setup_inputs():

    _w = (lambda a: (lambda t: t.to(torch.bfloat16) if t.is_floating_point() else t)(torch.as_tensor(a)))
    B, S, D = 2, 2048, 1024
    return {
        "x": _w((lambda *s: torch.randn(*s, dtype=torch.bfloat16) * 0.05)(B, S, D)),
        "g": _w((lambda *s: torch.randn(*s, dtype=torch.bfloat16) * 0.05)(D) + 1.0),
        "b": _w((lambda *s: torch.randn(*s, dtype=torch.bfloat16) * 0.4)(D)),
        "w": _w((lambda *s: torch.randn(*s, dtype=torch.bfloat16) * 0.05)(D, D)),
    }

def reference(x, g, b, w):
    return (_layernorm(x, axis=-1) * g + b) @ w
```

```cpp
#include <cuda_runtime.h>
#include <cuda_bf16.h>
#include <cuda.h>
#include <stdint.h>

namespace {

constexpr int M_TOTAL = 4096;
constexpr int N_TOTAL = 1024;
constexpr int K_TOTAL = 1024;
constexpr int BM = 128, BN = 256, BK = 64;
constexpr int STAGES = 4;
constexpr int KSTEPS = K_TOTAL / BK;
constexpr int N_TILES = N_TOTAL / BN;
constexpr int M_TILES = M_TOTAL / BM;
constexpr int NUM_CTAS = N_TILES * M_TILES;
constexpr int NUM_AUX = N_TILES;
constexpr int NUM_THREADS = 384;

constexpr int A_BYTES = BM * BK * 2;
constexpr int B_BYTES = BK * BN * 2;
constexpr int VEC_BYTES = K_TOTAL * 2;
constexpr int OFF_A = 0;
constexpr int OFF_B = OFF_A + STAGES * A_BYTES;
constexpr int OFF_BX = OFF_B + STAGES * B_BYTES;
constexpr int OFF_ROW = OFF_BX + 8 * BN * 2;
constexpr int ROW_PITCH = 64 * 16 + 32;
constexpr int OFF_XS = OFF_ROW + 4 * ROW_PITCH;
constexpr int OFF_PART = OFF_XS + 6 * 2048;
constexpr int OFF_G = OFF_PART + 2 * 32 * 8;
constexpr int OFF_BV = OFF_G + VEC_BYTES + 16;
constexpr int OFF_BAR = OFF_BV + VEC_BYTES + 112;
constexpr int OFF_LATE = OFF_BAR + 248;
constexpr int SMEM_BYTES = OFF_BAR + 256;

constexpr float LN_EPS = 1e-5f;
constexpr float MAX_MEAN_SQ = 16.f;
constexpr uint32_t SPIN_LIMIT = 65536;

constexpr uint32_t PF_B = 420;
constexpr uint32_t TMA0_LAG = 200;
constexpr uint32_t PF_1 = 950;
constexpr uint32_t PF_GAP = 650;
constexpr uint32_t TMA_LAG = 400;
constexpr uint32_t WARM_AT = 1250;
constexpr uint32_t STAT_AT = 2000;
constexpr uint32_t STAT_GAP = 300;
constexpr uint32_t SHIFT_AT = 13;
constexpr uint32_t G_POS = 6;

struct Inputs {
    const __nv_bfloat16* p[4];
    __nv_bfloat16* out;
};
struct Maps {
    CUtensorMap w, x, xs, o;
};

struct Scratch {
    ulonglong2 srec[M_TOTAL];
    uint4 cimg[N_TILES][256];
    unsigned int cflag[N_TILES * 32];
    unsigned int epoch[NUM_CTAS + NUM_AUX];
};
__device__ Scratch g_scratch;

__device__ __forceinline__ uint32_t smem_u32(const void* p) {
    return (uint32_t)__cvta_generic_to_shared(p);
}

__device__ __forceinline__ void mbar_init(uint32_t bar, uint32_t count) {
    asm volatile("mbarrier.init.shared::cta.b64 [%0], %1;" ::"r"(bar), "r"(count) : "memory");
}
__device__ __forceinline__ void mbar_expect_tx(uint32_t bar, uint32_t bytes) {
    asm volatile("mbarrier.arrive.expect_tx.shared::cta.b64 _, [%0], %1;" ::"r"(bar), "r"(bytes) : "memory");
}
__device__ __forceinline__ void mbar_arrive(uint32_t bar) {
    asm volatile("mbarrier.arrive.shared::cta.b64 _, [%0];" ::"r"(bar) : "memory");
}
__device__ __forceinline__ void mbar_wait(uint32_t bar, uint32_t parity) {
    asm volatile(
        "{\n.reg .pred p;\n"
        "RETRY:\n"
        ".pragma \"nounroll\";\n"
        "mbarrier.try_wait.parity.shared::cta.b64 p, [%0], %1;\n"
        "@!p bra.uni RETRY;\n}\n"
        ::"r"(bar), "r"(parity) : "memory");
}

__device__ __forceinline__ void tma_load_2d(uint32_t dst, const CUtensorMap* map, int c0, int c1, uint32_t bar) {
    asm volatile(
        "cp.async.bulk.tensor.2d.shared::cluster.global.mbarrier::complete_tx::bytes [%0], [%1, {%3, %4}], [%2];"
        ::"r"(dst), "l"(map), "r"(bar), "r"(c0), "r"(c1) : "memory");
}
__device__ __forceinline__ void tma_load_3d(uint32_t dst, const CUtensorMap* map, int c0, int c1, int c2, uint32_t bar) {
    asm volatile(
        "cp.async.bulk.tensor.3d.shared::cluster.global.mbarrier::complete_tx::bytes [%0], [%1, {%3, %4, %5}], [%2];"
        ::"r"(dst), "l"(map), "r"(bar), "r"(c0), "r"(c1), "r"(c2) : "memory");
}
__device__ __forceinline__ void bulk_load(uint32_t dst, const void* src, uint32_t bytes, uint32_t bar) {
    asm volatile(
        "cp.async.bulk.shared::cluster.global.mbarrier::complete_tx::bytes [%0], [%1], %2, [%3];"
        ::"r"(dst), "l"(src), "r"(bytes), "r"(bar) : "memory");
}
__device__ __forceinline__ void tma_store_2d(const CUtensorMap* map, uint32_t src, int c0, int c1) {
    asm volatile(
        "cp.async.bulk.tensor.2d.global.shared::cta.bulk_group [%0, {%2, %3}], [%1];"
        ::"l"(map), "r"(src), "r"(c0), "r"(c1) : "memory");
}
__device__ __forceinline__ void fence_async_smem() { asm volatile("fence.proxy.async.shared::cta;" ::: "memory"); }
__device__ __forceinline__ void prefetch_l2(const void* p) { asm volatile("prefetch.global.L2 [%0];" ::"l"(p)); }
__device__ __forceinline__ uint32_t clock32() {
    uint32_t c;
    asm volatile("mov.u32 %0, %%clock;" : "=r"(c));
    return c;
}
__device__ __forceinline__ bool elect_one() {
    uint32_t p;
    asm volatile("{\n.reg .pred p;\nelect.sync _|p, 0xffffffff;\nselp.u32 %0, 1, 0, p;\n}\n" : "=r"(p));
    return p != 0;
}
template <int ID, int COUNT>
__device__ __forceinline__ void bar_sync() { asm volatile("bar.sync %0, %1;" ::"n"(ID), "n"(COUNT) : "memory"); }
template <int ID, int COUNT>
__device__ __forceinline__ void bar_arrive() { asm volatile("bar.arrive %0, %1;" ::"n"(ID), "n"(COUNT) : "memory"); }

__device__ __forceinline__ void rec_store(ulonglong2* p, uint32_t w0, uint32_t w1, uint32_t tag) {
    asm volatile(
        "{\n.reg .b64 a, b;\nmov.b64 a, {%1, %3};\nmov.b64 b, {%2, %3};\n"
        "st.relaxed.gpu.global.v2.b64 [%0], {a, b};\n}\n"
        ::"l"(p), "r"(w0), "r"(w1), "r"(tag) : "memory");
}
__device__ __forceinline__ uint4 rec_load(const ulonglong2* p) {
    uint4 r;
    asm volatile(
        "{\n.reg .b64 a, b;\nld.relaxed.gpu.global.v2.b64 {a, b}, [%4];\n"
        "mov.b64 {%0, %1}, a;\nmov.b64 {%2, %3}, b;\n}\n"
        : "=r"(r.x), "=r"(r.y), "=r"(r.z), "=r"(r.w) : "l"(p) : "memory");
    return r;
}

__device__ __forceinline__ void ldsm_x4(uint32_t addr, uint32_t& r0, uint32_t& r1, uint32_t& r2, uint32_t& r3) {
    asm volatile("ldmatrix.sync.aligned.m8n8.x4.shared.b16 {%0, %1, %2, %3}, [%4];"
                 : "=r"(r0), "=r"(r1), "=r"(r2), "=r"(r3) : "r"(addr) : "memory");
}
__device__ __forceinline__ void ldsm_x4_t(uint32_t addr, uint32_t& r0, uint32_t& r1, uint32_t& r2, uint32_t& r3) {
    asm volatile("ldmatrix.sync.aligned.m8n8.x4.trans.shared.b16 {%0, %1, %2, %3}, [%4];"
                 : "=r"(r0), "=r"(r1), "=r"(r2), "=r"(r3) : "r"(addr) : "memory");
}
__device__ __forceinline__ void stsm_x4(uint32_t addr, uint32_t r0, uint32_t r1, uint32_t r2, uint32_t r3) {
    asm volatile("stmatrix.sync.aligned.m8n8.x4.shared.b16 [%0], {%1, %2, %3, %4};"
                 ::"r"(addr), "r"(r0), "r"(r1), "r"(r2), "r"(r3) : "memory");
}
__device__ __forceinline__ void sts32(uint32_t addr, uint32_t v) {
    asm volatile("st.shared.b32 [%0], %1;" ::"r"(addr), "r"(v) : "memory");
}
__device__ __forceinline__ void sts128(uint32_t addr, uint32_t a, uint32_t b, uint32_t c, uint32_t d) {
    asm volatile("st.shared.v4.b32 [%0], {%1, %2, %3, %4};" ::"r"(addr), "r"(a), "r"(b), "r"(c), "r"(d) : "memory");
}
__device__ __forceinline__ uint4 lds128(uint32_t addr) {
    uint4 v;
    asm volatile("ld.shared.v4.b32 {%0, %1, %2, %3}, [%4];"
                 : "=r"(v.x), "=r"(v.y), "=r"(v.z), "=r"(v.w) : "r"(addr) : "memory");
    return v;
}
__device__ __forceinline__ uint32_t lds32(uint32_t addr) {
    uint32_t v;
    asm volatile("ld.shared.b32 %0, [%1];" : "=r"(v) : "r"(addr) : "memory");
    return v;
}

__device__ __forceinline__ void wgmma_fence() { asm volatile("wgmma.fence.sync.aligned;" ::: "memory"); }
__device__ __forceinline__ void wgmma_commit() { asm volatile("wgmma.commit_group.sync.aligned;" ::: "memory"); }
template <int N>
__device__ __forceinline__ void wgmma_wait() { asm volatile("wgmma.wait_group.sync.aligned %0;" ::"n"(N) : "memory"); }

#define ACC8(b) "+f"(d[(b) + 0]), "+f"(d[(b) + 1]), "+f"(d[(b) + 2]), "+f"(d[(b) + 3]), \
                "+f"(d[(b) + 4]), "+f"(d[(b) + 5]), "+f"(d[(b) + 6]), "+f"(d[(b) + 7])

template <int H>
__device__ __forceinline__ void wgmma_rs_n128(float (&d)[128], const uint32_t* a, uint64_t desc_b,
                                              uint32_t accumulate = 1) {
    asm volatile(
        "{\n.reg .pred p;\nsetp.ne.b32 p, %69, 0;\n"
        "wgmma.mma_async.sync.aligned.m64n128k16.f32.bf16.bf16 "
        "{%0, %1, %2, %3, %4, %5, %6, %7, %8, %9, %10, %11, %12, %13, %14, %15, "
        "%16, %17, %18, %19, %20, %21, %22, %23, %24, %25, %26, %27, %28, %29, %30, %31, "
        "%32, %33, %34, %35, %36, %37, %38, %39, %40, %41, %42, %43, %44, %45, %46, %47, "
        "%48, %49, %50, %51, %52, %53, %54, %55, %56, %57, %58, %59, %60, %61, %62, %63}, "
        "{%64, %65, %66, %67}, %68, p, 1, 1, 1;\n}\n"
        : ACC8(64 * H), ACC8(64 * H + 8), ACC8(64 * H + 16), ACC8(64 * H + 24),
          ACC8(64 * H + 32), ACC8(64 * H + 40), ACC8(64 * H + 48), ACC8(64 * H + 56)
        : "r"(a[0]), "r"(a[1]), "r"(a[2]), "r"(a[3]), "l"(desc_b), "r"(accumulate));
}

__device__ __forceinline__ uint64_t make_desc(uint32_t addr, uint32_t lbo, uint32_t sbo) {
    return (uint64_t)((addr & 0x3FFFF) >> 4) | ((uint64_t)(lbo >> 4) << 16) | ((uint64_t)(sbo >> 4) << 32) |
           ((uint64_t)1 << 62);
}
constexpr int D_STAGE = B_BYTES >> 4, D_CHUNK = 2048 >> 4, D_HALF = D_STAGE / 2;

__device__ __forceinline__ uint32_t mul_bf16x2(uint32_t a, uint32_t b) {
    uint32_t r;
    asm("mul.rn.bf16x2 %0, %1, %2;" : "=r"(r) : "r"(a), "r"(b));
    return r;
}
__device__ __forceinline__ uint32_t pack_bf16x2(float lo, float hi) {
    uint32_t r;
    asm("cvt.rn.bf16x2.f32 %0, %1, %2;" : "=r"(r) : "f"(hi), "f"(lo));
    return r;
}
__device__ __forceinline__ float bf_lo(uint32_t v) { return __uint_as_float(v << 16); }
__device__ __forceinline__ float bf_hi(uint32_t v) { return __uint_as_float(v & 0xffff0000u); }

__device__ __forceinline__ void accum_stats(uint32_t v, float& s, float& q) {
    const float lo = bf_lo(v), hi = bf_hi(v);
    s += lo;
    q = fmaf(lo, lo, q);
    s += hi;
    q = fmaf(hi, hi, q);
}

__device__ __forceinline__ void load_x_frag(uint32_t (&a)[16], const uint32_t (&a_addr)[4], uint32_t a_off) {
#pragma unroll
    for (int j = 0; j < 4; j++) ldsm_x4(a_addr[j] + a_off, a[4 * j], a[4 * j + 1], a[4 * j + 2], a[4 * j + 3]);
}
__device__ __forceinline__ void mul_a(uint32_t (&dst)[16], const uint32_t (&a)[16], const uint32_t (&gv)[8]) {
#pragma unroll
    for (int j = 0; j < 16; j++) dst[j] = mul_bf16x2(a[j], gv[j >> 1]);
#pragma unroll
    for (int j = 0; j < 16; j++) asm volatile("" : "+r"(dst[j]));
}

#define ISSUE_REGION(zero, ...)                 \
    do {                                        \
        uint32_t n_ = (zero);                   \
        _Pragma("unroll 1") do { __VA_ARGS__; } while (n_-- != 0); \
    } while (0)

__device__ __forceinline__ void turn_wait(int wg) { asm volatile("bar.sync %0, 256;" ::"r"(6 + wg) : "memory"); }
__device__ __forceinline__ void turn_pass(int wg) { asm volatile("bar.arrive %0, 256;" ::"r"(7 - wg) : "memory"); }

template <int H>
__device__ __forceinline__ void half_step(float (&acc)[128], const uint32_t (&a)[16], uint64_t d) {
#pragma unroll
    for (int j = 0; j < 4; j++) wgmma_rs_n128<H>(acc, &a[4 * j], d + j * D_CHUNK + H * D_HALF);
}

__device__ __forceinline__ void split_dup(float v, uint32_t& hi, uint32_t& lo) {
    hi = pack_bf16x2(v, v);
    const float rem = v - bf_hi(hi);
    lo = pack_bf16x2(rem, rem);
}

template <int Q>
__device__ __forceinline__ void epi_stage(float (&acc)[128], float rs0, float rs1, const uint32_t (&a_addr)[4]) {
#pragma unroll
    for (int i = 0; i < 32; i++) asm volatile("" : "+f"(acc[32 * Q + i])::"memory");
#pragma unroll
    for (int p = 0; p < 4; p++) {
        const float* d = &acc[32 * Q + 8 * p];
        stsm_x4(a_addr[p] + Q * A_BYTES, pack_bf16x2(rs0 * d[0], rs0 * d[1]), pack_bf16x2(rs1 * d[2], rs1 * d[3]),
                pack_bf16x2(rs0 * d[4], rs0 * d[5]), pack_bf16x2(rs1 * d[6], rs1 * d[7]));
    }
}

__device__ __forceinline__ void mma_gb(float (&d)[4], uint32_t a0, uint32_t a2, uint32_t b0, uint32_t b1) {
    asm volatile("mma.sync.aligned.m16n8k16.row.col.f32.bf16.bf16.f32 {%0, %1, %2, %3}, {%4, %8, %5, %8}, {%6, %7}, {%0, %1, %2, %3};"
                 : "+f"(d[0]), "+f"(d[1]), "+f"(d[2]), "+f"(d[3]) : "r"(a0), "r"(a2), "r"(b0), "r"(b1), "r"(0u));
}
__device__ __forceinline__ uint32_t cpair_off(int grp, int lane, int r) {
    const int row = (lane & 4) + r;
    return (grp >> 3) * 1024 + row * 128 + (((grp & 7) ^ row) << 4) + (lane & 3) * 4;
}
__device__ __forceinline__ void split_pair(const float (&d)[4], uint32_t& hi, uint32_t& lo) {
    hi = pack_bf16x2(d[0], d[1]);
    lo = pack_bf16x2(d[0] - bf_lo(hi), d[1] - bf_hi(hi));
}

__device__ __forceinline__ float warp_sum(float v) {
#pragma unroll
    for (int o = 16; o > 0; o >>= 1) v += __shfl_xor_sync(0xffffffffu, v, o);
    return v;
}

__device__ __forceinline__ void redo_rows(const Inputs& in, int row0, int col0, uint32_t buf, uint32_t mr, int lane) {
    const __nv_bfloat16* x = in.p[0] + (size_t)row0 * K_TOTAL;
#pragma unroll 1
    for (int r = 0; r < 16; r++) {
        const uint32_t* xr = reinterpret_cast<const uint32_t*>(x + r * K_TOTAL) + lane;
        float s = 0.f, q = 0.f;
#pragma unroll 1
        for (int i = 0; i < K_TOTAL / 64; i++) s += bf_lo(xr[i * 32]) + bf_hi(xr[i * 32]);
        const float mean = warp_sum(s) * (1.0f / K_TOTAL);
#pragma unroll 1
        for (int i = 0; i < K_TOTAL / 64; i++) {
            const float lo = bf_lo(xr[i * 32]) - mean, hi = bf_hi(xr[i * 32]) - mean;
            q = fmaf(lo, lo, fmaf(hi, hi, q));
        }
        const float rstd = rsqrtf(warp_sum(q) * (1.0f / K_TOTAL) + LN_EPS);
        if (lane < 2) sts32(mr + r * 8 + lane * 4, __float_as_uint(lane ? rstd : mean));
    }
    float o[16][8] = {};
#pragma unroll 1
    for (int k0 = 0; k0 < K_TOTAL; k0 += 32) {
        __syncwarp();
        const float gk = __bfloat162float(in.p[2][k0 + lane]), bk = __bfloat162float(in.p[3][k0 + lane]);
#pragma unroll 1
        for (int r = 0; r < 16; r++) {
            const float c = __bfloat162float(x[r * K_TOTAL + k0 + lane]) - __uint_as_float(lds32(mr + r * 8));
            sts32(buf + lane * 64 + r * 4, __float_as_uint(fmaf(c * __uint_as_float(lds32(mr + r * 8 + 4)), gk, bk)));
        }
        __syncwarp();
#pragma unroll 1
        for (int kk = 0; kk < 32; kk++) {
            const uint4 wv = *reinterpret_cast<const uint4*>(in.p[1] + (size_t)(k0 + kk) * N_TOTAL + col0 + lane * 8);
            const float w[8] = {bf_lo(wv.x), bf_hi(wv.x), bf_lo(wv.y), bf_hi(wv.y),
                                bf_lo(wv.z), bf_hi(wv.z), bf_lo(wv.w), bf_hi(wv.w)};
#pragma unroll
            for (int i = 0; i < 4; i++) {
                const uint4 yv = lds128(buf + kk * 64 + i * 16);
                const float y[4] = {__uint_as_float(yv.x), __uint_as_float(yv.y), __uint_as_float(yv.z),
                                    __uint_as_float(yv.w)};
#pragma unroll
                for (int r = 0; r < 4; r++)
#pragma unroll
                    for (int c = 0; c < 8; c++) o[4 * i + r][c] = fmaf(y[r], w[c], o[4 * i + r][c]);
            }
        }
    }
#pragma unroll
    for (int r = 0; r < 16; r++)
        *reinterpret_cast<uint4*>(in.out + (size_t)(row0 + r) * N_TOTAL + col0 + lane * 8) =
            make_uint4(pack_bf16x2(o[r][0], o[r][1]), pack_bf16x2(o[r][2], o[r][3]), pack_bf16x2(o[r][4], o[r][5]),
                       pack_bf16x2(o[r][6], o[r][7]));
}

constexpr int BAR_FULL = OFF_BAR, BAR_W0 = OFF_BAR + 32, BAR_X0 = OFF_BAR + 40, BAR_G = OFF_BAR + 56;
constexpr int BAR_EMPTY = OFF_BAR + 96, BAR_C = BAR_EMPTY + 32, BAR_XS = BAR_EMPTY + 40;

template <bool ALL_RESIDENT>
__global__ void __launch_bounds__(NUM_THREADS, 1)
ln_linear_kernel(const __grid_constant__ Inputs in, Scratch* __restrict__ scr, const __grid_constant__ Maps maps) {
    const uint32_t t0 = clock32();
    extern __shared__ __align__(1024) uint8_t smem_raw[];
    const uint32_t sbase = smem_u32(smem_raw);

    const uint32_t zero = blockIdx.y;
    const uint32_t bx = blockIdx.x;
    const uint32_t cta = ALL_RESIDENT ? (bx < 8 ? bx : bx < 10 ? bx + 120 : bx < 130 ? bx - 2 : bx)
                                      : (bx < NUM_AUX ? bx + NUM_CTAS : bx - NUM_AUX);
    const bool aux = cta >= NUM_CTAS;

    const int tid = threadIdx.x;
    {
        const uint32_t sel = aux ? 2 : (tid >> 4) & 1;
        const uint32_t i = cta * 16 + tid;
        uint32_t line;
        asm("{\n.reg .pred q;\nsetp.eq.u32 q, %3, 0;\nselp.b32 %0, %1, %2, q;\n}\n"
            : "=r"(line) : "r"((i + (i & ~63u)) * 16), "r"((aux ? 0 : cta * 8 - 16) + tid), "r"(sel));
        const __nv_bfloat16* p = in.p[sel] + (size_t)line * 64;
        if (tid < (aux ? 16 : 24)) prefetch_l2(p);
    }
    const __nv_bfloat16* const xptr = in.p[0];
    const __nv_bfloat16* const wptr = in.p[1];
    const __nv_bfloat16* const gptr = in.p[2];
    const __nv_bfloat16* const bptr = in.p[3];
    const int lane = tid & 31;
    const int warp = __shfl_sync(0xffffffffu, tid >> 5, 0);
    const uint32_t nt = cta % N_TILES;
    const uint32_t mt = cta / N_TILES;

    auto load_w = [&](int ks, uint32_t bar) {
        tma_load_3d(sbase + OFF_B + (ks % STAGES) * B_BYTES, &maps.w, 0, ks * BK, nt * 4, bar);
    };
    auto load_x = [&](int ks, uint32_t bar) {
        tma_load_3d(sbase + OFF_A + (ks % STAGES) * A_BYTES, &maps.x, 0, mt * BM, ks, bar);
        tma_load_3d(sbase + OFF_A + (ks % STAGES) * A_BYTES + A_BYTES / 2, &maps.x, 0, mt * BM + 64, ks, bar);
    };

    const bool leader = elect_one();
    const uint32_t own_bar = sbase + OFF_BAR + 8 * warp;
    mbar_init(own_bar, 1);
    asm volatile("fence.mbarrier_init.release.cluster;" ::: "memory");
    __syncwarp();
    if (leader && warp == 7) {
        mbar_expect_tx(own_bar, aux ? 2 * VEC_BYTES : VEC_BYTES);
        bulk_load(sbase + OFF_G, gptr, VEC_BYTES, own_bar);
        if (aux) bulk_load(sbase + OFF_BV, bptr, VEC_BYTES, own_bar);
    }
    __syncwarp();
    if (leader && (uint32_t)(warp - 4) < (aux ? 1u : 3u)) {
        const bool is_x = warp > 4;
        mbar_expect_tx(own_bar, is_x ? A_BYTES / 2 : B_BYTES);
        if (warp == 6) while (clock32() - t0 < PF_B + TMA0_LAG) {}
        tma_load_3d(sbase + (is_x ? OFF_A + (warp - 5) * (A_BYTES / 2) : OFF_B), &maps.w + (is_x ? 1 : 0), 0,
                    is_x ? mt * BM + (warp - 5) * 64 : 0, is_x ? 0 : nt * 4, own_bar);
    }
    if (warp == 1 && !aux) {
        while (clock32() - t0 < PF_B) {}
        if (lane < 16) prefetch_l2(xptr + (mt * BM + 64 + nt * 16 + lane) * K_TOTAL);
        while (clock32() - t0 < PF_1) {}
        prefetch_l2(xptr + (cta * 32 + lane) * K_TOTAL + BK);
        if (lane < 8) prefetch_l2(wptr + BK * N_TOTAL + (cta * 8 + lane) * 64);
    }
    if (leader && warp == 3) {
#pragma unroll
        for (int s = 0; s < STAGES; s++) mbar_init(sbase + BAR_EMPTY + 8 * s, 8);
        mbar_init(sbase + BAR_C, 3);
#pragma unroll
        for (int i = 0; i < 6; i++) mbar_init(sbase + BAR_XS + 8 * i, 1);
        asm volatile("fence.mbarrier_init.release.cluster;" ::: "memory");
    }
    __syncwarp();

    if (warp >= 8) {
        asm volatile("setmaxnreg.dec.sync.aligned.u32 40;");
        if (warp == 8) {
            bar_sync<2, NUM_THREADS>();
            if (leader) {
                mbar_arrive(sbase + BAR_FULL);
#pragma unroll 1
                for (int u = 1; u < KSTEPS; u++) {
                    const uint32_t fb = sbase + BAR_FULL + 8 * (u % STAGES);
                    if (u >= STAGES) mbar_wait(sbase + BAR_EMPTY + 8 * (u % STAGES), ((u / STAGES) - 1) & 1);
                    else while (clock32() - t0 < PF_1 + TMA_LAG + (u - 1) * PF_GAP) {}
                    const bool x_now = !aux && u <= (int)SHIFT_AT, x_next = !aux && u >= (int)SHIFT_AT && u + 1 < KSTEPS;
                    mbar_expect_tx(fb, B_BYTES + (x_now ? A_BYTES : 0) + (x_next ? A_BYTES : 0));
                    if (x_now) load_x(u, fb);
                    load_w(u, fb);
                    if (x_next) load_x(u + 1, fb);
                }
                asm volatile("prefetch.tensormap [%0];" ::"l"(&maps.o) : "memory");
            }
        } else {
            bar_sync<2, NUM_THREADS>();
            if (!aux) {
                const int hw = warp - 9, t = tid - 288;
                if (hw < 2) {
                    while (clock32() - t0 < PF_1 + (hw + 1) * PF_GAP) {}
                    prefetch_l2(xptr + (cta * 32 + lane) * K_TOTAL + (hw + 2) * BK);
                    if (lane < 8) prefetch_l2(wptr + (hw + 2) * (BK * N_TOTAL) + (cta * 8 + lane) * 64);
                }

                const uint32_t slot = sbase + OFF_XS + hw * 4096, bar = sbase + BAR_XS + 16 * hw;
                auto fetch = [&](uint32_t n, int cb) {
                    mbar_expect_tx(bar + (n & 1) * 8, 2048);
                    tma_load_2d(slot + (n & 1) * 2048, &maps.xs, cb * 32, cta * 32, bar + (n & 1) * 8);
                };
                while (clock32() - t0 < STAT_AT + hw * STAT_GAP) {}
                if (leader) {
                    fetch(0, hw);
                    fetch(1, hw + 3);
                }
                const uint32_t tag = scr->epoch[cta] + 1;
                float sum = 0.f, sq = 0.f;
                uint32_t it = 0;
#pragma unroll 1
                for (int cb = hw; cb < K_TOTAL / 32; cb += 3, it++) {
                    mbar_wait(bar + (it & 1) * 8, (it >> 1) & 1);
                    uint4 v[4];
#pragma unroll
                    for (int j = 0; j < 4; j++)
                        v[j] = lds128(slot + (it & 1) * 2048 + lane * 64 + (((j + (lane >> 1)) & 3) << 4));
                    const uint32_t dep = (v[0].x | v[1].x | v[2].x | v[3].x) & zero;
                    if (leader && cb + 6 < K_TOTAL / 32) fetch(it, cb + 6 + dep);
                    __syncwarp();
#pragma unroll
                    for (int j = 0; j < 4; j++) {
                        accum_stats(v[j].x, sum, sq);
                        accum_stats(v[j].y, sum, sq);
                        accum_stats(v[j].z, sum, sq);
                        accum_stats(v[j].w, sum, sq);
                    }
                }
                if (hw > 0) {
                    sts32(sbase + OFF_PART + (t - 32) * 8, __float_as_uint(sum));
                    sts32(sbase + OFF_PART + (t - 32) * 8 + 4, __float_as_uint(sq));
                }
                if (hw == 2) {
                    bar_arrive<1, 96>();
                    if (leader) {
                        uint32_t seen, spins = 0;
#pragma unroll 1
                        do {
                            asm volatile("ld.acquire.gpu.global.u32 %0, [%1];"
                                         : "=r"(seen) : "l"(&scr->cflag[nt * 32]) : "memory");
                        } while (seen != tag && ++spins < SPIN_LIMIT);
                        asm volatile("fence.proxy.async.global;" ::: "memory");
                        sts32(sbase + OFF_LATE, seen ^ tag);
                        mbar_expect_tx(sbase + BAR_C, 4096);
                        bulk_load(sbase + OFF_BX, scr->cimg[nt], 4096, sbase + BAR_C);
                    }
                } else {
                    bar_sync<1, 96>();
                    if (hw == 0) {
#pragma unroll
                        for (int i = 0; i < 2; i++) {
                            sum += __uint_as_float(lds32(sbase + OFF_PART + (i * 32 + lane) * 8));
                            sq += __uint_as_float(lds32(sbase + OFF_PART + (i * 32 + lane) * 8 + 4));
                        }
                        const float mean = sum * (1.0f / K_TOTAL);
                        const float var = fmaxf(fmaf(-mean, mean, sq * (1.0f / K_TOTAL)), 0.f) + LN_EPS;
                        rec_store(&scr->srec[cta * 32 + lane], __float_as_uint(mean), __float_as_uint(var), tag);
                        if (lane == 0) scr->epoch[cta] = tag;
                    }
                    bar_sync<4, 64>();
                    __nanosleep(250);

                    const ulonglong2* rec = &scr->srec[mt * BM + (t >> 3) * 16 + (t & 7)];
                    uint4 r0, r1;
                    uint32_t spins = 0;
#pragma unroll 1
                    do {
                        r0 = rec_load(rec);
                        r1 = rec_load(rec + 8);
                    } while ((r0.y != tag || r0.w != tag || r1.y != tag || r1.w != tag) && ++spins < SPIN_LIMIT);
                    const float m0 = __uint_as_float(r0.x), v0 = __uint_as_float(r0.z);
                    const float m1 = __uint_as_float(r1.x), v1 = __uint_as_float(r1.z);
                    float rs0 = rsqrtf(v0), rs1 = rsqrtf(v1);
                    uint32_t e0[4], e1[4];
                    split_dup(-m0, e0[0], e0[1]);
                    split_dup(v0 * rs0, e0[2], e0[3]);
                    split_dup(-m1, e1[0], e1[1]);
                    split_dup(v1 * rs1, e1[2], e1[3]);
                    if (m0 * m0 > MAX_MEAN_SQ * v0 || m1 * m1 > MAX_MEAN_SQ * v1 || spins == SPIN_LIMIT) rs0 = -1.f;
#pragma unroll
                    for (int q = 0; q < 4; q++)
                        sts128(sbase + OFF_ROW + t * 16 + q * ROW_PITCH, e0[q], e1[q], __float_as_uint(rs0),
                               __float_as_uint(rs1));
                    __syncwarp();
                    if (leader) mbar_arrive(sbase + BAR_C);
                }
            }
        }
    } else {
        asm volatile("setmaxnreg.inc.sync.aligned.u32 232;");
        float acc[128];
        uint32_t a[16], raw[16], gv[8];

        const int wg = warp >> 2;
        uint32_t a_addr[4];
#pragma unroll
        for (int j = 0; j < 4; j++) {
            a_addr[j] = sbase + OFF_A + (warp * 16 + (lane & 15)) * 128 + ((((lane >> 4) + 2 * j) ^ (lane & 7)) << 4);
            asm volatile("" : "+r"(a_addr[j]));
        }
        const uint32_t g_base = sbase + OFF_G + (lane >> 3) * 16;
        const uint64_t desc = make_desc(sbase + OFF_B, 8192, 1024) + zero;

        bar_sync<2, NUM_THREADS>();
        if (wg == 1) {
            while (clock32() - t0 < WARM_AT) {}
            wgmma_fence();
            wgmma_commit();
            wgmma_wait<0>();
        }
        mbar_wait(sbase + BAR_G, 0);
        if (aux) {
            float d[4][4] = {};
            const uint32_t tag = scr->epoch[cta] + 1;
            const uint32_t va = sbase + ((lane & 7) == 1 ? OFF_BV : OFF_G) + (lane >> 3) * 16;
            const uint32_t wa = sbase + OFF_B + (warp >> 1) * 8192 + (lane & 15) * 128;
            const uint32_t c0 = (warp & 1) * 4 + (lane >> 4);
            mbar_wait(sbase + BAR_W0, 0);
#pragma unroll 1
            for (int ks = 0; ks < KSTEPS; ks++) {
                const int s = ks % STAGES;
                uint32_t v[8], dep = 0;
                ldsm_x4(va + ks * 128, v[0], v[1], v[2], v[3]);
                ldsm_x4(va + ks * 128 + 64, v[4], v[5], v[6], v[7]);
                mbar_wait(sbase + BAR_FULL + 8 * s, (ks / STAGES) & 1);
#pragma unroll
                for (int j = 0; j < 4; j++) {
#pragma unroll
                    for (int h = 0; h < 2; h++) {
                        uint32_t w0, w1, w2, w3;
                        ldsm_x4_t(wa + s * B_BYTES + j * 2048 + (((c0 + 2 * h) ^ (lane & 7)) << 4), w0, w1, w2, w3);
                        mma_gb(d[2 * h], v[2 * j], v[2 * j + 1], w0, w1);
                        mma_gb(d[2 * h + 1], v[2 * j], v[2 * j + 1], w2, w3);
                        dep |= w0;
                    }
                }
                if (leader) mbar_arrive(sbase + BAR_EMPTY + 8 * s + (dep & zero));
            }
            if (lane < 8) {
#pragma unroll
                for (int i = 0; i < 4; i++) {
                    uint32_t hi, lo;
                    split_pair(d[i], hi, lo);
#pragma unroll
                    for (int r = 0; r < 4; r++) sts32(sbase + OFF_BX + cpair_off(warp * 4 + i, lane, r), (r & 1) ? lo : hi);
                }
            }
            bar_sync<3, 256>();
            scr->cimg[nt][tid] = lds128(sbase + OFF_BX + tid * 16);
            bar_sync<3, 256>();
            if (tid == 0) {
                asm volatile("st.release.gpu.global.u32 [%0], %1;" ::"l"(&scr->cflag[nt * 32]), "r"(tag) : "memory");
                scr->epoch[cta] = tag;
            }
            return;
        }
        if (wg == 1) turn_pass(1);

        ldsm_x4(g_base, gv[0], gv[1], gv[2], gv[3]);
        ldsm_x4(g_base + 64, gv[4], gv[5], gv[6], gv[7]);
        uint32_t g13[8], g14[8], g15[8];
        ldsm_x4(g_base + 13 * 128, g13[0], g13[1], g13[2], g13[3]);
        ldsm_x4(g_base + 13 * 128 + 64, g13[4], g13[5], g13[6], g13[7]);
        ldsm_x4(g_base + 14 * 128, g14[0], g14[1], g14[2], g14[3]);
        ldsm_x4(g_base + 14 * 128 + 64, g14[4], g14[5], g14[6], g14[7]);
        ldsm_x4(g_base + 15 * 128, g15[0], g15[1], g15[2], g15[3]);
        ldsm_x4(g_base + 15 * 128 + 64, g15[4], g15[5], g15[6], g15[7]);
        mbar_wait(sbase + BAR_X0 + 8 * wg, 0);
        load_x_frag(raw, a_addr, 0);
        mul_a(a, raw, gv);
        mbar_wait(sbase + BAR_W0, 0);

        const uint32_t my_turn = 6 + wg, other_turn = 7 - wg;
        uint32_t g_next = g_base + 128;
        uint64_t d = desc;
        const uint32_t exit1 = wg ? (KSTEPS - 5) * 8 : 1;
#pragma unroll 1
        for (uint32_t k8 = 0;; k8 += 8) {
            asm volatile("bar.sync %0, 256;" ::"r"(my_turn) : "memory");
            wgmma_fence();
#pragma unroll
            for (int i = 0; i < 8; i++) {
                if (i == G_POS) {
                    asm volatile("bar.arrive %0, 256;" ::"r"(other_turn) : "memory");
                    if (k8 != (KSTEPS - 4) * 8) {
                        ldsm_x4(g_next, gv[0], gv[1], gv[2], gv[3]);
                        ldsm_x4(g_next + 64, gv[4], gv[5], gv[6], gv[7]);
                    }
                }
                if (i & 1) wgmma_rs_n128<1>(acc, &a[4 * (i >> 1)], d + (i >> 1) * D_CHUNK + D_HALF, i > 1 ? 1 : k8);
                else wgmma_rs_n128<0>(acc, &a[4 * (i >> 1)], d + (i >> 1) * D_CHUNK, i > 1 ? 1 : k8);
            }
            wgmma_commit();
            mbar_wait(sbase + BAR_FULL + ((k8 + 8) & 24), ((k8 + 8) >> 5) & 1);
            load_x_frag(raw, a_addr, ((k8 + 8) & 24) * (A_BYTES / 8));
            if (k8 == (KSTEPS - 4) * 8) break;
            const uint32_t release = sbase + BAR_EMPTY + (k8 & 24) + ((raw[3] | raw[7] | raw[11] | raw[15]) & zero);
            g_next += 128;
            d = desc + ((k8 + 8) & 24) * (D_STAGE / 8);
            wgmma_wait<0>();
            if (leader) mbar_arrive(release);
            mul_a(a, raw, gv);
            if (k8 == exit1) break;
        }

        uint32_t a14[16], a15[16], ax[4];
        const uint64_t d13 = desc + D_STAGE, d14 = desc + 2 * D_STAGE, d15 = desc + 3 * D_STAGE;
        const uint64_t desc_x = make_desc(sbase + OFF_BX, 1024, 0);
        auto load_pair = [&](uint32_t (&f)[16], int j, uint32_t off) {
            ldsm_x4(a_addr[j] + off, f[4 * j], f[4 * j + 1], f[4 * j + 2], f[4 * j + 3]);
            ldsm_x4(a_addr[j + 1] + off, f[4 * j + 4], f[4 * j + 5], f[4 * j + 6], f[4 * j + 7]);
        };
        uint4 rowc = make_uint4(0, 0, 0, 0);
        if (wg == 1) {
            turn_wait(1);
            mbar_wait(sbase + BAR_FULL + 8 * 1, 1);
            mbar_wait(sbase + BAR_FULL + 8 * 2, 1);
            bar_sync<5, 256>();
            mbar_wait(sbase + BAR_FULL + 8 * 3, 1);
            mbar_wait(sbase + BAR_C, 0);
            load_x_frag(raw, a_addr, 1 * A_BYTES);
            rowc = lds128(sbase + OFF_ROW + (tid >> 2) * 16 + (tid & 3) * ROW_PITCH);
            bar_sync<3, 256>();
            wgmma_fence();
            half_step<0>(acc, a, desc);
            wgmma_commit();
        }
        load_pair(a14, 0, 2 * A_BYTES);
        mul_a(raw, raw, g13);
        wgmma_fence();
        half_step<0>(acc, raw, d13);
        wgmma_commit();
        if (wg == 0) mbar_wait(sbase + BAR_FULL + 8 * 2, 1);
        load_pair(a14, 2, 2 * A_BYTES);
        load_pair(a15, 0, 3 * A_BYTES);
        mul_a(a14, a14, g14);
        wgmma_fence();
        half_step<0>(acc, a14, d14);
        wgmma_commit();
        ISSUE_REGION(zero, load_pair(a15, 2, 3 * A_BYTES));
        mul_a(a15, a15, g15);
        if (wg == 0) mbar_wait(sbase + BAR_FULL + 8 * 3, 1);
        wgmma_fence();
        half_step<0>(acc, a15, d15);
        wgmma_commit();
        if (wg == 0) {
            mbar_wait(sbase + BAR_C, 0);
            rowc = lds128(sbase + OFF_ROW + (tid >> 2) * 16 + (tid & 3) * ROW_PITCH);
        }
        ax[0] = rowc.x, ax[1] = rowc.y, ax[2] = ax[3] = 0;
        const float rs0 = __uint_as_float(rowc.z), rs1 = __uint_as_float(rowc.w);
        wgmma_fence();
        wgmma_rs_n128<0>(acc, ax, desc_x);
        wgmma_commit();
        if (wg == 0) bar_arrive<5, 256>();
        wgmma_fence();
        half_step<1>(acc, raw, d13);
        half_step<1>(acc, a14, d14);
        wgmma_commit();

        const uint32_t src = sbase + OFF_A + warp * 2048;
        const int col = nt * BN, orow = mt * BM + warp * 16;

        auto flush = [&](int q) {
            fence_async_smem();
            __syncwarp();
            if (leader) tma_store_2d(&maps.o, src + q * A_BYTES, col + q * 64, orow);
        };
        wgmma_wait<1>();
        epi_stage<0>(acc, rs0, rs1, a_addr);
        flush(0);
        epi_stage<1>(acc, rs0, rs1, a_addr);
        wgmma_fence();
        half_step<1>(acc, a15, d15);
        wgmma_rs_n128<1>(acc, ax, desc_x + 128);
        wgmma_commit();
        if (wg == 0) bar_arrive<3, 256>();
        flush(1);
        if (wg == 1) {
            wgmma_fence();
            half_step<1>(acc, a, desc);
            wgmma_commit();
        }
        wgmma_wait<0>();
        epi_stage<2>(acc, rs0, rs1, a_addr);
        flush(2);
        epi_stage<3>(acc, rs0, rs1, a_addr);
        if (wg == 0) {
            flush(3);
        } else {
            __syncwarp();
            const uint32_t rd = src + 3 * A_BYTES + (lane >> 3) * 128 + (((lane & 7) ^ (lane >> 3)) << 4);
            uint4* dst = reinterpret_cast<uint4*>(in.out + (size_t)(orow + (lane >> 3)) * N_TOTAL + col + 192) + (lane & 7);
            uint4 o[4];
#pragma unroll
            for (int i = 0; i < 4; i++) o[i] = lds128((rd ^ ((i & 1) << 6)) + i * 512);
#pragma unroll
            for (int i = 0; i < 4; i++) dst[i * (4 * N_TOTAL / 8)] = o[i];
        }
        const uint32_t late = lds32(sbase + OFF_LATE);
        if (leader) {
            asm volatile("cp.async.bulk.commit_group;" ::: "memory");
            asm volatile("cp.async.bulk.wait_group.read 0;" ::: "memory");
        }
        if (__any_sync(0xffffffffu, rs0 < 0.f || late != 0)) {
            if (leader) asm volatile("cp.async.bulk.wait_group 0;\nfence.proxy.async;" ::: "memory");
            __syncwarp();
            redo_rows(in, orow, col, src, src + A_BYTES, lane);
        }
    }
}

typedef CUresult (*EncodeTiledFn)(CUtensorMap*, CUtensorMapDataType, cuuint32_t, void*, const cuuint64_t*,
                                  const cuuint64_t*, const cuuint32_t*, const cuuint32_t*, CUtensorMapInterleave,
                                  CUtensorMapSwizzle, CUtensorMapL2promotion, CUtensorMapFloatOOBfill);

}

extern "C" void kernel_launch(void* const* d_in, const int* in_sizes, int n_in, void* d_out, int out_size) {
    (void)in_sizes; (void)n_in; (void)out_size;
    const __nv_bfloat16* x = (const __nv_bfloat16*)d_in[0];
    const __nv_bfloat16* g = (const __nv_bfloat16*)d_in[1];
    const __nv_bfloat16* b = (const __nv_bfloat16*)d_in[2];
    const __nv_bfloat16* w = (const __nv_bfloat16*)d_in[3];

    static EncodeTiledFn encode = nullptr;
    static Scratch* scr = nullptr;
    static bool all_resident = false;
    if (!encode) {
        void* fn = nullptr;
        cudaDriverEntryPointQueryResult qr;
        cudaGetDriverEntryPoint("cuTensorMapEncodeTiled", &fn, cudaEnableDefault, &qr);
        encode = (EncodeTiledFn)fn;
        cudaFuncSetAttribute(ln_linear_kernel<true>, cudaFuncAttributeMaxDynamicSharedMemorySize, SMEM_BYTES);
        cudaFuncSetAttribute(ln_linear_kernel<false>, cudaFuncAttributeMaxDynamicSharedMemorySize, SMEM_BYTES);
        cudaGetSymbolAddress((void**)&scr, g_scratch);
        int dev = 0, sms = 0;
        cudaGetDevice(&dev);
        cudaDeviceGetAttribute(&sms, cudaDevAttrMultiProcessorCount, dev);
        all_resident = sms >= NUM_CTAS + NUM_AUX;
    }

    const Inputs in = {{x, w, g, b}, (__nv_bfloat16*)d_out};
    Maps maps;
    const cuuint32_t es[3] = {1, 1, 1};
    for (int i = 0; i < 2; i++) {
        cuuint64_t dims[3] = {64, (cuuint64_t)(i ? M_TOTAL : K_TOTAL), 16};
        cuuint64_t strides[2] = {2048, 128};
        cuuint32_t box[3] = {64, 64, (cuuint32_t)(i ? 1 : 4)};
        encode(i ? &maps.x : &maps.w, CU_TENSOR_MAP_DATA_TYPE_BFLOAT16, 3, (void*)(i ? x : w), dims, strides, box, es,
               CU_TENSOR_MAP_INTERLEAVE_NONE, CU_TENSOR_MAP_SWIZZLE_128B, CU_TENSOR_MAP_L2_PROMOTION_L2_128B,
               CU_TENSOR_MAP_FLOAT_OOB_FILL_NONE);
    }
    for (int i = 0; i < 2; i++) {
        cuuint64_t dims[2] = {1024, M_TOTAL};
        cuuint64_t strides[1] = {2048};
        cuuint32_t box[2] = {(cuuint32_t)(i ? 64 : 32), (cuuint32_t)(i ? 16 : 32)};
        encode(i ? &maps.o : &maps.xs, CU_TENSOR_MAP_DATA_TYPE_BFLOAT16, 2, i ? d_out : (void*)x, dims, strides, box, es,
               CU_TENSOR_MAP_INTERLEAVE_NONE, i ? CU_TENSOR_MAP_SWIZZLE_128B : CU_TENSOR_MAP_SWIZZLE_NONE,
               i ? CU_TENSOR_MAP_L2_PROMOTION_NONE : CU_TENSOR_MAP_L2_PROMOTION_L2_128B,
               CU_TENSOR_MAP_FLOAT_OOB_FILL_NONE);
    }

    if (all_resident) ln_linear_kernel<true><<<NUM_CTAS + NUM_AUX, NUM_THREADS, SMEM_BYTES>>>(in, scr, maps);
    else ln_linear_kernel<false><<<NUM_CTAS + NUM_AUX, NUM_THREADS, SMEM_BYTES>>>(in, scr, maps);
}
```
